```python
import torch

def _softmax(x, axis=-1):
    return torch.softmax(x, dim=axis)
def _gelu(x):
    return torch.nn.functional.gelu(x, approximate="tanh")
def _silu(x):
    return torch.nn.functional.silu(x)
def _sigmoid(x):
    return torch.sigmoid(x)
def _layernorm(x, axis=-1, eps=1e-5):
    m = x.mean(dim=axis, keepdim=True)
    v = x.var(dim=axis, keepdim=True, unbiased=False)
    return (x - m) / torch.sqrt(v + eps)
def _scatter_add(tgt, idx, src, axis=0):
    return tgt.clone().index_add_(axis, idx, src)
def _segment_sum(src, seg, n):
    out = torch.zeros((n,) + src.shape[1:], dtype=src.dtype)
    return out.index_add_(0, seg, src)
def _pad(x, pw):
    flat = tuple(v for pair in reversed(pw) for v in pair)
    return torch.nn.functional.pad(x, flat)

kernel_name = 'sequential_preLN__sliding_block_cached__moe_arch_mod__decode'

def setup_inputs():

    _w = (lambda a: (lambda t: t.to(torch.bfloat16) if t.is_floating_point() else t)(torch.as_tensor(a)))
    def _A_setup():
        B, Sq, D = 2, 1, 512
        Hq, Hkv, Sk, Dh = 32, 32, 16384, 128
        assert Hq % Hkv == 0, (Hq, Hkv)
        return {
            "x": _w((lambda *s: torch.randn(*s, dtype=torch.bfloat16) * 0.05)(B, Sq, D)),
            "k_cache": _w((lambda *s: torch.randn(*s, dtype=torch.bfloat16) * 3.2)(B, Hkv, Sk, Dh)),
            "v_cache": _w((lambda *s: torch.randn(*s, dtype=torch.bfloat16) * 0.4)(B, Hkv, Sk, Dh)),
            "wq": _w((lambda *s: torch.randn(*s, dtype=torch.bfloat16) * 3.2)(D, Hq * Dh) * (D ** -0.5)),
            "wo": _w((lambda *s: torch.randn(*s, dtype=torch.bfloat16) * 0.4)(Hq * Dh, D) * ((Hq * Dh) ** -0.5)),
        }
    _A_in = _A_setup()

    def _B_setup():
        B, S, D, F, C = 2, 1, 512, 1376, 1
        return {
            "x": _w((lambda *s: torch.randn(*s, dtype=torch.bfloat16) * 0.05)(B, S, D)),
            "w_r": _w((lambda *s: torch.randn(*s, dtype=torch.bfloat16) * 3.2)(D)),
            "w_gate": _w((lambda *s: torch.randn(*s, dtype=torch.bfloat16) * 0.1)(D, F)),
            "w_up": _w((lambda *s: torch.randn(*s, dtype=torch.bfloat16) * 0.1)(D, F)),
            "w_down": _w((lambda *s: torch.randn(*s, dtype=torch.bfloat16) * 0.1)(F, D)),
        }
    _B_in = _B_setup()

    return {
        "A_x": _A_in["x"],
        "A_k_cache": _A_in["k_cache"],
        "A_v_cache": _A_in["v_cache"],
        "A_wq": _A_in["wq"],
        "A_wo": _A_in["wo"],
        "B_x": _B_in["x"],
        "B_w_r": _B_in["w_r"],
        "B_w_gate": _B_in["w_gate"],
        "B_w_up": _B_in["w_up"],
        "B_w_down": _B_in["w_down"],
    }

def reference(A_x, A_k_cache, A_v_cache, A_wq, A_wo, B_x, B_w_r, B_w_gate, B_w_up, B_w_down):
    def _A_ref(x, k_cache, v_cache, wq, wo):
        B, Sq, D = x.shape
        Hq, Dh = 32, 128
        Hkv, Sk = k_cache.shape[1], k_cache.shape[2]
        W = min(4096, max(256, Sk // 4))
        rep = Hq // Hkv
        q = (lambda x, *d: x.permute(*d))((x @ wq).reshape(B, Sq, Hq, Dh), 0, 2, 1, 3)
        k = (lambda x, n, axis: torch.repeat_interleave(x, n, dim=axis))(k_cache[:, :, Sk - W:, :], rep, axis=1)
        v = (lambda x, n, axis: torch.repeat_interleave(x, n, dim=axis))(v_cache[:, :, Sk - W:, :], rep, axis=1)
        scores = torch.einsum("bhqd,bhkd->bhqk", q, k) * (Dh ** -0.5)
        p = _softmax(scores, axis=-1)
        o = torch.einsum("bhqk,bhkd->bhqd", p, v)
        return (lambda x, *d: x.permute(*d))(o, 0, 2, 1, 3).reshape(B, Sq, Hq * Dh) @ wo

    def _B_ref(x, w_r, w_gate, w_up, w_down):
        B, S, D = x.shape
        C = 1
        r = x @ w_r
        idx = torch.argsort(-r, axis=-1)[:, :C]
        idx_e = (lambda x, n, axis: torch.repeat_interleave(x, n, dim=axis))(idx.reshape(B, C, 1), D, axis=2)
        x_sel = (lambda x, i, axis: torch.take_along_dim(x, i, dim=axis))(x, idx_e, axis=1)
        g = _silu(x_sel @ w_gate)
        u = x_sel @ w_up
        y = (g * u) @ w_down
        r_sel = _sigmoid((lambda x, i, axis: torch.take_along_dim(x, i, dim=axis))(r, idx, axis=1))
        y = y * r_sel.reshape(B, C, 1)
        b_off = (torch.arange(B) * S).reshape(B, 1)
        flat_idx = (idx + b_off).reshape(B * C)
        zero = (x * 0.0).reshape(B * S, D)
        upd = _scatter_add(zero, flat_idx, y.reshape(B * C, D), axis=0)
        return x + upd.reshape(B, S, D)

    x = A_x
    h = x + _A_ref(_layernorm(x, axis=-1), A_k_cache, A_v_cache, A_wq, A_wo)
    h2 = h + _B_ref(_layernorm(h, axis=-1), B_w_r, B_w_gate, B_w_up, B_w_down)
    return h2
```

```cpp
#include <cuda_runtime.h>
#include <cuda.h>
#include <cuda_bf16.h>
#include <stdint.h>

namespace {

constexpr int DM   = 512;
constexpr int NH   = 32;
constexpr int DH   = 128;
constexpr int SK   = 16384;
constexpr int WIN  = 4096;
constexpr int FF   = 1376;
constexpr int UKEYS = 64;
constexpr int UPB   = WIN / UKEYS;
constexpr int NSTR  = 128;
constexpr int NCTA  = NSTR + 4;
constexpr int NFFN  = FF / 16;
constexpr int NRED  = 32;
constexpr int TILE_BYTES = UKEYS * DH * 2;
constexpr int NSTAGE = 8;
constexpr int NTHREADS = 17 * 32;
constexpr int SPIN_LIMIT = 1 << 20;
constexpr double PACE_EFF = 0.97;
constexpr int FIRST_OFF = 12;
constexpr int CAP_TILES = 5;
constexpr int LAT_HI = 1900, LAT_HI2 = 1500, LATE_FROM = 52;
constexpr int GAIN16 = 3, RSH = 7;
constexpr int END_DELAY = 450;
constexpr int GO_WAIT = 1700, WD_WAIT = 2900;
constexpr int XLAT = 1200;

__device__ uint32_t g_epoch;
__device__ __align__(128) uint32_t g_q[64 * DH];
__device__ __align__(128) uint32_t g_po[64 * UPB * DH];
__device__ __align__(128) uint32_t g_pml[64 * UPB * 32];
__device__ __align__(128) uint32_t g_run[4 * 2 * DM];
__device__ __align__(128) uint32_t g_yp[NFFN * 2 * DM];

__device__ __forceinline__ uint32_t smem_u32(const void* p) { return (uint32_t)__cvta_generic_to_shared(p); }
__device__ __forceinline__ void mbar_init(uint32_t bar, uint32_t cnt) {
    asm volatile("mbarrier.init.shared::cta.b64 [%0], %1;" ::"r"(bar), "r"(cnt));
}
__device__ __forceinline__ void mbar_expect_tx(uint32_t bar, uint32_t bytes) {
    asm volatile("mbarrier.arrive.expect_tx.shared::cta.b64 _, [%0], %1;" ::"r"(bar), "r"(bytes) : "memory");
}
__device__ __forceinline__ void mbar_arrive(uint32_t bar) {
    asm volatile("mbarrier.arrive.shared::cta.b64 _, [%0];" ::"r"(bar) : "memory");
}
__device__ __forceinline__ void mbar_wait(uint32_t bar, uint32_t parity) {
    asm volatile("{\n.reg .pred p;\nWAIT_LOOP%=:\nmbarrier.try_wait.parity.shared::cta.b64 p, [%0], %1;\n"
                 "@p bra DONE%=;\nbra WAIT_LOOP%=;\nDONE%=:\n}\n" ::"r"(bar), "r"(parity) : "memory");
}
__device__ __forceinline__ bool mbar_test(uint32_t bar, uint32_t parity) {
    uint32_t r;
    asm volatile("{\n.reg .pred p;\nmbarrier.test_wait.parity.shared::cta.b64 p, [%1], %2;\nselp.u32 %0, 1, 0, p;\n}\n"
                 : "=r"(r) : "r"(bar), "r"(parity) : "memory");
    return r != 0;
}
__device__ __forceinline__ void tensor_load3(uint32_t dst, const CUtensorMap* tm, int c1, uint32_t bar, uint64_t pol) {
    asm volatile("cp.async.bulk.tensor.3d.shared::cluster.global.mbarrier::complete_tx::bytes.L2::cache_hint "
                 "[%0], [%1, {%2, %3, %2}], [%4], %5;"
                 ::"r"(dst), "l"(tm), "r"(0), "r"(c1), "r"(bar), "l"(pol) : "memory");
}
__device__ __forceinline__ void cp_async16(uint32_t dst, const void* src) {
    asm volatile("cp.async.cg.shared.global.L2::128B [%0], [%1], 16;" ::"r"(dst), "l"(src) : "memory");
}
template <int ID, int N> __device__ __forceinline__ void bar_sync() { asm volatile("bar.sync %0, %1;" ::"n"(ID), "n"(N) : "memory"); }
template <int ID, int N> __device__ __forceinline__ void bar_arrive() { asm volatile("bar.arrive %0, %1;" ::"n"(ID), "n"(N) : "memory"); }
__device__ __forceinline__ uint32_t gtimer() {
    uint32_t t;
    asm volatile("mov.u32 %0, %globaltimer_lo;" : "=r"(t));
    return t;
}
__device__ __forceinline__ uint4 ld_poll16(const uint32_t* p) {
    uint4 v;
    asm volatile("ld.relaxed.gpu.global.v4.u32 {%0,%1,%2,%3}, [%4];"
                 : "=r"(v.x), "=r"(v.y), "=r"(v.z), "=r"(v.w) : "l"(p) : "memory");
    return v;
}
__device__ __forceinline__ uint2 ld_poll8(const uint32_t* p) {
    uint2 v;
    asm volatile("ld.relaxed.gpu.global.v2.u32 {%0,%1}, [%2];" : "=r"(v.x), "=r"(v.y) : "l"(p) : "memory");
    return v;
}
__device__ __forceinline__ uint32_t ld_poll4(const uint32_t* p) {
    uint32_t v;
    asm volatile("ld.relaxed.gpu.global.u32 %0, [%1];" : "=r"(v) : "l"(p) : "memory");
    return v;
}
__device__ __forceinline__ void st_pub4(uint32_t* p, uint32_t v) {
    asm volatile("st.relaxed.gpu.global.u32 [%0], %1;" ::"l"(p), "r"(v) : "memory");
}
__device__ __forceinline__ void st_pub8(uint32_t* p, uint32_t a, uint32_t b) {
    asm volatile("st.relaxed.gpu.global.v2.u32 [%0], {%1,%2};" ::"l"(p), "r"(a), "r"(b) : "memory");
}
__device__ __forceinline__ void st_pub16(uint32_t* p, uint32_t a, uint32_t b, uint32_t c, uint32_t d) {
    asm volatile("st.relaxed.gpu.global.v4.u32 [%0], {%1,%2,%3,%4};" ::"l"(p), "r"(a), "r"(b), "r"(c), "r"(d) : "memory");
}
__device__ __forceinline__ bool tag_ok(const uint2& v, uint32_t tag) { return (((v.x ^ tag) | (v.y ^ tag)) & 3u) == 0u; }
__device__ __forceinline__ uint32_t tagf(float f, uint32_t tag) { return (__float_as_uint(f) & ~3u) | tag; }
__device__ __forceinline__ float untag(uint32_t w) { return __uint_as_float(w & ~3u); }
__device__ __forceinline__ uint32_t tag_bad(const uint4& v, uint32_t tag) {
    return ((v.x ^ tag) | (v.y ^ tag)) | ((v.z ^ tag) | (v.w ^ tag));
}
template <int N>
__device__ __forceinline__ void poll_all(uint4 (&u)[N], const uint32_t* p, int stride, uint32_t tag) {
#pragma unroll 1
    for (int it = 0; it < SPIN_LIMIT; it++) {
        uint32_t bad = 0;
#pragma unroll
        for (int i = 0; i < N; i++) u[i] = ld_poll16(p + i * stride);
#pragma unroll
        for (int i = 0; i < N; i++) bad |= tag_bad(u[i], tag);
        if (__all_sync(0xffffffffu, (bad & 3u) == 0u)) break;
    }
}

__device__ __forceinline__ float bf_lo(uint32_t w) { return __uint_as_float(w << 16); }
__device__ __forceinline__ float bf_hi(uint32_t w) { return __uint_as_float(w & 0xffff0000u); }
__device__ __forceinline__ uint32_t cvt2(float lo, float hi) {
    uint32_t r;
    asm("cvt.rn.bf16x2.f32 %0, %1, %2;" : "=r"(r) : "f"(hi), "f"(lo));
    return r;
}
__device__ __forceinline__ float rbf(float f) { return __uint_as_float(cvt2(0.f, f)); }
__device__ __forceinline__ float ex2(float x) { float r; asm("ex2.approx.ftz.f32 %0, %1;" : "=f"(r) : "f"(x)); return r; }
__device__ __forceinline__ float rcp(float x) { float r; asm("rcp.approx.ftz.f32 %0, %1;" : "=f"(r) : "f"(x)); return r; }
__device__ __forceinline__ float sqrt_a(float x) { float r; asm("sqrt.approx.ftz.f32 %0, %1;" : "=f"(r) : "f"(x)); return r; }
__device__ __forceinline__ void acc4(float (&a)[4], const uint4& v) {
    a[0] += untag(v.x); a[1] += untag(v.y); a[2] += untag(v.z); a[3] += untag(v.w);
}
__device__ __forceinline__ float sum4(const uint4 (&u)[4], int r) {
    const uint32_t* p = reinterpret_cast<const uint32_t*>(u);
    return (untag(p[r]) + untag(p[4 + r])) + (untag(p[8 + r]) + untag(p[12 + r]));
}
__device__ __forceinline__ void mma_bf16(float (&c)[4], const uint4& a, uint32_t b0, uint32_t b1) {
    asm volatile("mma.sync.aligned.m16n8k16.row.col.f32.bf16.bf16.f32 {%0,%1,%2,%3}, {%4,%5,%6,%7}, {%8,%9}, {%0,%1,%2,%3};"
                 : "+f"(c[0]), "+f"(c[1]), "+f"(c[2]), "+f"(c[3])
                 : "r"(a.x), "r"(a.y), "r"(a.z), "r"(a.w), "r"(b0), "r"(b1));
}
__device__ __forceinline__ uint4 ldsm(uint32_t addr) {
    uint4 r;
    asm volatile("ldmatrix.sync.aligned.m8n8.x4.shared.b16 {%0,%1,%2,%3}, [%4];"
                 : "=r"(r.x), "=r"(r.y), "=r"(r.z), "=r"(r.w) : "r"(addr) : "memory");
    return r;
}
__device__ __forceinline__ uint4 ldsm_t(uint32_t addr) {
    uint4 r;
    asm volatile("ldmatrix.sync.aligned.m8n8.x4.trans.shared.b16 {%0,%1,%2,%3}, [%4];"
                 : "=r"(r.x), "=r"(r.y), "=r"(r.z), "=r"(r.w) : "r"(addr) : "memory");
    return r;
}
__device__ __forceinline__ float4 pick_quad(const float (&c)[4][4], int t) {
    const bool rb = t & 1, hp = t & 2;
    const float r0 = hp ? (rb ? c[2][1] : c[2][0]) : (rb ? c[0][1] : c[0][0]);
    const float r1 = hp ? (rb ? c[2][3] : c[2][2]) : (rb ? c[0][3] : c[0][2]);
    const float r2 = hp ? (rb ? c[3][1] : c[3][0]) : (rb ? c[1][1] : c[1][0]);
    const float r3 = hp ? (rb ? c[3][3] : c[3][2]) : (rb ? c[1][3] : c[1][2]);
    return make_float4(r0, r1, r2, r3);
}
__device__ __forceinline__ float fold_t(const float (&a)[4], int lane) {
    const bool h16 = lane & 16, h8 = lane & 8;
    float ka = h16 ? a[2] : a[0], kb = h16 ? a[3] : a[1];
    ka += __shfl_xor_sync(0xffffffffu, h16 ? a[0] : a[2], 16);
    kb += __shfl_xor_sync(0xffffffffu, h16 ? a[1] : a[3], 16);
    return (h8 ? kb : ka) + __shfl_xor_sync(0xffffffffu, h8 ? ka : kb, 8);
}

constexpr float LOG2E = 1.4426950408889634f;
constexpr int BAR_C = 1, BAR_L = 2, BAR_H = 3, BAR_Q = 4, BAR_Q2 = 5, BAR_Q1 = 6;

struct __align__(1024) Smem {
    unsigned char ring[NSTAGE][TILE_BYTES];
    unsigned char wbuf[2 * 16384];
    uint32_t q[NH * DH / 2];
    float ca[576];
    __align__(16) unsigned short ps[8 * 128];
    float cst[16];
    float red[8 * 144];
    float st[64];
    uint64_t full[NSTAGE], empty[NSTAGE], pfull[8], dfull;
    uint32_t tag;
    volatile int done;
    volatile int go;
};

__device__ __forceinline__ void wait_ge(volatile int* p, int v, int ns = 50) {
    if ((threadIdx.x & 31) == 0)
        for (int it = 0; *p < v && it < SPIN_LIMIT; it++) __nanosleep(ns);
    __syncwarp();
}

__device__ __forceinline__ void ln_part1(const float (&v)[4], float* st, int warp, int lane) {
    float m = ((v[0] + v[1]) + (v[2] + v[3])) * 0.25f;
    const float d0 = v[0] - m, d1 = v[1] - m, d2 = v[2] - m, d3 = v[3] - m;
    float q = fmaf(d0, d0, d1 * d1) + fmaf(d2, d2, d3 * d3);
#pragma unroll
    for (int o = 1; o < 16; o <<= 1) {
        const float mo = __shfl_xor_sync(0xffffffffu, m, o), qo = __shfl_xor_sync(0xffffffffu, q, o);
        const float d = m - mo;
        q = fmaf(d * d, 2.0f * o, q + qo);
        m = (m + mo) * 0.5f;
    }
    if ((lane & 15) == 0) { st[(lane >> 4) * 16 + warp] = m; st[(lane >> 4) * 16 + 8 + warp] = q; }
}
__device__ __forceinline__ void ln_part2(const float* st, int b, float& mr, float& inv) {
    const float4 ma = *reinterpret_cast<const float4*>(st + b * 16);
    const float4 mb = *reinterpret_cast<const float4*>(st + b * 16 + 4);
    const float4 qa = *reinterpret_cast<const float4*>(st + b * 16 + 8);
    const float4 qb = *reinterpret_cast<const float4*>(st + b * 16 + 12);
    const float mean = (((ma.x + ma.y) + (ma.z + ma.w)) + ((mb.x + mb.y) + (mb.z + mb.w))) * 0.125f;
    float dv = 0.f, dw = 0.f, t;
    t = ma.x - mean; dv = fmaf(t, t, dv); t = ma.y - mean; dw = fmaf(t, t, dw);
    t = ma.z - mean; dv = fmaf(t, t, dv); t = ma.w - mean; dw = fmaf(t, t, dw);
    t = mb.x - mean; dv = fmaf(t, t, dv); t = mb.y - mean; dw = fmaf(t, t, dw);
    t = mb.z - mean; dv = fmaf(t, t, dv); t = mb.w - mean; dw = fmaf(t, t, dw);
    const float tot = (((qa.x + qa.y) + (qa.z + qa.w)) + ((qb.x + qb.y) + (qb.z + qb.w))) + 64.0f * (dv + dw);
    const float var = rbf(tot * (1.0f / 512.0f));
    mr  = rbf(mean);
    inv = rcp(rbf(sqrt_a(rbf(var + 1e-5f))));
}
__device__ __forceinline__ void layernorm_2x512(float (&v)[4], float* st, int warp, int lane) {
    ln_part1(v, st, warp, lane);
    bar_sync<BAR_H, 256>();
    float mr, inv;
    ln_part2(st, lane >> 4, mr, inv);
#pragma unroll
    for (int i = 0; i < 4; i++) v[i] = rbf(rbf(v[i] - mr) * inv);
}

__device__ __forceinline__ void gemv32(const uint4 (&w)[4][2], uint32_t p0, uint32_t p1, float* red, int warp, int lane) {
    const int g = lane >> 2, t = lane & 3;
    float c[2][2][4];
#pragma unroll
    for (int i = 0; i < 4; i++) c[0][0][i] = c[0][1][i] = c[1][0][i] = c[1][1][i] = 0.f;
#pragma unroll
    for (int s = 0; s < 4; s++) {
        const int src = ((g & 1) << 4) + 4 * s + t;
        uint32_t b0 = __shfl_sync(0xffffffffu, p0, src);
        uint32_t b1 = __shfl_sync(0xffffffffu, p1, src);
        if (g & 2) b0 = b1 = 0x3f803f80u;
        mma_bf16(c[s & 1][0], w[s][0], b0, b1);
        mma_bf16(c[s & 1][1], w[s][1], b0, b1);
    }
    const int mu = t >> 1;
    const float a0 = mu ? c[0][1][0] + c[1][1][0] : c[0][0][0] + c[1][0][0];
    const float a1 = mu ? c[0][1][1] + c[1][1][1] : c[0][0][1] + c[1][0][1];
    const float a2 = mu ? c[0][1][2] + c[1][1][2] : c[0][0][2] + c[1][0][2];
    const float a3 = mu ? c[0][1][3] + c[1][1][3] : c[0][0][3] + c[1][0][3];
    float* r = red + warp * 144 + (t & 1) * 72 + mu * 16 + g;
    r[0] = a0; r[36] = a1; r[8] = a2; r[44] = a3;
}

__device__ __forceinline__ void wo_job(float (&c)[4][4], int h, int j, int warp, int lane, uint32_t tag, uint32_t wsm,
                                       int bar, float* red, float* st, uint32_t t0, int pace_ns16) {
    const int g = lane >> 2, t = lane & 3, sub = lane >> 3;
    uint4 w[2][4];
    const int lrow = (lane & 7) + (lane >> 4) * 8;
#pragma unroll
    for (int s = 0; s < 2; s++)
#pragma unroll
        for (int mu = 0; mu < 4; mu++)
            w[s][mu] = ldsm_t(wsm + warp * 4096 + (s * 16 + lrow) * 128 + (((2 * mu + ((lane >> 3) & 1)) ^ (lane & 7)) << 4));
    {
        const int iv = 2 * h + 1;
        const int tp = max(((FIRST_OFF * pace_ns16) >> 4) + iv * pace_ns16 +
                           (h == NH - 1 ? 0 : XLAT * 16), (6800 + 850 * h) * 16);
#pragma unroll 1
        for (int it = 0; (int)((gtimer() - t0) << 4) < tp && it < 4096; it++) __nanosleep(40);
    }
    const int slot = ((warp >> 2) * NH + h) * UPB + (warp & 3) * 16;
    const uint32_t* mp = g_pml + (slot + (lane & 15)) * 32;
    const uint32_t* pp = g_po + (slot + sub) * DH + j * 32 + (lane & 7) * 4;
    uint4 pv[4];
    uint2 ml = ld_poll8(mp);
    if (h == NH - 1) {
#pragma unroll 1
        for (int it = 0; it < SPIN_LIMIT && !__all_sync(0xffffffffu, tag_ok(ml, tag)); it++) ml = ld_poll8(mp);
    }
#pragma unroll
    for (int i = 0; i < 4; i++) pv[i] = ld_poll16(pp + i * 4 * DH);
#pragma unroll 1
    for (int it = 0; it < SPIN_LIMIT && !__all_sync(0xffffffffu, tag_ok(ml, tag)); it++) ml = ld_poll8(mp);
    float sc[4];
    {
        const float m = untag(ml.x);
        float M = m;
#pragma unroll
        for (int o = 1; o < 16; o <<= 1) M = fmaxf(M, __shfl_xor_sync(0xffffffffu, M, o));
        if (lane == 0) st[warp] = M;
        asm volatile("bar.sync %0, 256;" ::"r"(bar) : "memory");
        const float4 ma = *reinterpret_cast<const float4*>(st + (warp & 4));
        M = fmaxf(fmaxf(ma.x, ma.y), fmaxf(ma.z, ma.w));
        const float e = ex2((m - M) * LOG2E);
        float L = e * untag(ml.y);
#pragma unroll
        for (int o = 1; o < 16; o <<= 1) L += __shfl_xor_sync(0xffffffffu, L, o);
        if (lane == 0) st[8 + warp] = L;
#pragma unroll
        for (int i = 0; i < 4; i++) sc[i] = __shfl_sync(0xffffffffu, e, i * 4 + sub);
    }
#pragma unroll 1
    for (int it = 0; it < SPIN_LIMIT; it++) {
        const bool b0 = tag_bad(pv[0], tag) & 3u, b1 = tag_bad(pv[1], tag) & 3u;
        const bool b2 = tag_bad(pv[2], tag) & 3u, b3 = tag_bad(pv[3], tag) & 3u;
        if (!__any_sync(0xffffffffu, b0 | b1 | b2 | b3)) break;
        if (b0) pv[0] = ld_poll16(pp);
        if (b1) pv[1] = ld_poll16(pp + 4 * DH);
        if (b2) pv[2] = ld_poll16(pp + 8 * DH);
        if (b3) pv[3] = ld_poll16(pp + 12 * DH);
    }
    {
        float a[4];
        a[0] = (sc[0] * untag(pv[0].x) + sc[1] * untag(pv[1].x)) + (sc[2] * untag(pv[2].x) + sc[3] * untag(pv[3].x));
        a[1] = (sc[0] * untag(pv[0].y) + sc[1] * untag(pv[1].y)) + (sc[2] * untag(pv[2].y) + sc[3] * untag(pv[3].y));
        a[2] = (sc[0] * untag(pv[0].z) + sc[1] * untag(pv[1].z)) + (sc[2] * untag(pv[2].z) + sc[3] * untag(pv[3].z));
        a[3] = (sc[0] * untag(pv[0].w) + sc[1] * untag(pv[1].w)) + (sc[2] * untag(pv[2].w) + sc[3] * untag(pv[3].w));
        red[(warp & 3) * 64 + (warp >> 2) * 32 + (lane & 7) * 4 + sub] = fold_t(a, lane);
    }
    asm volatile("bar.sync %0, 256;" ::"r"(bar) : "memory");
    {
        const float4 la = *reinterpret_cast<const float4*>(st + 8 + (lane >> 4) * 4);
        const float2 z0 = *reinterpret_cast<const float2*>(red + lane * 2), z1 = *reinterpret_cast<const float2*>(red + 64 + lane * 2);
        const float2 z2 = *reinterpret_cast<const float2*>(red + 128 + lane * 2), z3 = *reinterpret_cast<const float2*>(red + 192 + lane * 2);
        const float inv = rcp((la.x + la.y) + (la.z + la.w));
        const uint32_t pr = cvt2(((z0.x + z1.x) + (z2.x + z3.x)) * inv, ((z0.y + z1.y) + (z2.y + z3.y)) * inv);
        const int src = ((g & 1) << 4) + 2 * t;
        const uint32_t b0 = __shfl_sync(0xffffffffu, pr, src), b1 = __shfl_sync(0xffffffffu, pr, src + 1);
        const uint32_t b2 = __shfl_sync(0xffffffffu, pr, src + 8), b3 = __shfl_sync(0xffffffffu, pr, src + 9);
#pragma unroll
        for (int mu = 0; mu < 4; mu++) mma_bf16(c[mu], w[0][mu], b0, b1);
#pragma unroll
        for (int mu = 0; mu < 4; mu++) mma_bf16(c[mu], w[1][mu], b2, b3);
    }
}

__global__ void __launch_bounds__(NTHREADS, 1)
fused_decode_kernel(const __grid_constant__ CUtensorMap tm_o, const __grid_constant__ CUtensorMap tm_d,
                    const __grid_constant__ CUtensorMap tm_k, const __grid_constant__ CUtensorMap tm_v,
                    const __nv_bfloat16* __restrict__ wq,
                    const __nv_bfloat16* __restrict__ x,
                    const __nv_bfloat16* __restrict__ wr,
                    const __nv_bfloat16* __restrict__ wg, const __nv_bfloat16* __restrict__ wu,
                    __nv_bfloat16* __restrict__ out, int pace_ns16) {
    extern __shared__ __align__(1024) unsigned char smem_raw[];
    Smem& sm = *reinterpret_cast<Smem*>(smem_raw);
    const int lane = threadIdx.x & 31, wid = threadIdx.x >> 5;
    const int bid = blockIdx.x;
    const int cb = bid >> 6, tile = bid & 63;
    const bool is_x = bid >= NSTR;
    const uint32_t wb = smem_u32(sm.wbuf);

    if (wid == 16) {
        uint64_t pol;
        asm volatile("createpolicy.fractional.L2::evict_first.b64 %0, 1.0;" : "=l"(pol));
        const uint32_t dfull = smem_u32(&sm.dfull);
        const uint32_t t0 = gtimer();
        const int row0 = cb * NH * SK + (SK - WIN) + tile * UKEYS;
        if (lane < 2) asm volatile("prefetch.tensormap [%0];" ::"l"(is_x ? &tm_o : (lane ? &tm_v : &tm_k)) : "memory");
        if (lane < NSTAGE) { mbar_init(smem_u32(&sm.full[lane]), 1); mbar_init(smem_u32(&sm.empty[lane]), is_x ? 8 : 4); mbar_init(smem_u32(&sm.pfull[lane]), 4); }
        if (lane == NSTAGE) { mbar_init(dfull, 1); sm.done = 0; sm.go = 0; }
        asm volatile("fence.mbarrier_init.release.cluster;" ::: "memory");
        __syncthreads();
        if (is_x) {
            if (lane == 0) {
#pragma unroll 1
                for (int n = 0; n < NH; n++) {
                    mbar_wait(smem_u32(&sm.empty[n & 3]), ((n >> 2) & 1) ^ 1);
                    mbar_expect_tx(smem_u32(&sm.full[n & 3]), 32768);
                    tensor_load3(smem_u32(sm.ring) + (n & 3) * 32768, &tm_o, n * DH + (bid - NSTR) * 32,
                                 smem_u32(&sm.full[n & 3]), pol);
                }
            }
            return;
        }
        uint32_t tnext16 = (uint32_t)((FIRST_OFF * pace_ns16) >> 4);
        int st = 0, ph = 1, wst = 0, wph = 0, nland = 0, slip = 0;
        uint32_t tiss = 0;
#pragma unroll 1
        for (int i = 0; i < 2 * NH; i++) {
            mbar_wait(smem_u32(&sm.empty[st]), ph);
            uint32_t now;
            int spins = 0;
            for (;;) {
                now = __shfl_sync(0xffffffffu, gtimer() - t0, 0);
                const bool landed = __all_sync(0xffffffffu, nland < i && mbar_test(smem_u32(&sm.full[wst]), wph));
                if (landed) {
                    const int lat = (int)(now - __shfl_sync(0xffffffffu, tiss, wst));
                    const int over = lat - (nland >= LATE_FROM ? LAT_HI2 : LAT_HI);
                    if (over > 0 && nland >= 6) { tnext16 += over * GAIN16; slip += over * GAIN16; }
                    nland++;
                    if (++wst == NSTAGE) { wst = 0; wph ^= 1; }
                }
                if (i - nland < CAP_TILES && ((int)((now << 4) - tnext16) >= 0 || ++spins > 256)) break;
            }
            tnext16 += pace_ns16 - (slip >> RSH);
            slip -= slip >> RSH;
            if (lane == st) tiss = now;
            if (lane == 0) {
                mbar_expect_tx(smem_u32(&sm.full[st]), TILE_BYTES);
                tensor_load3(smem_u32(sm.ring[st]), (i & 1) ? &tm_v : &tm_k, 2 * (row0 + (i >> 1) * SK), smem_u32(&sm.full[st]), pol);
            }
            __syncwarp();
            if (++st == NSTAGE) { st = 0; ph ^= 1; }
        }
        tnext16 += END_DELAY * 16;
        if (lane == 0) {
            long long c0 = clock64();
            while ((int)(((gtimer() - t0) << 4) - tnext16) < 0 && clock64() - c0 < 8000) {}
            c0 = clock64();
            sm.go = 1;
            while (clock64() - c0 < GO_WAIT) {}
            sm.go = 2;
            while (clock64() - c0 < WD_WAIT) {}
            if (bid < NFFN) {
                mbar_wait(smem_u32(&sm.empty[st]), ph);
                mbar_expect_tx(dfull, 16384);
                tensor_load3(smem_u32(sm.ring[st]), &tm_d, bid * 16, dfull, pol);
            }
        }
        return;
    }

    if (is_x) {
        const int grp = wid >> 3, warp = wid & 7;
        const int g = lane >> 2, t = lane & 3;
        const uint32_t tag = (ld_poll4(&g_epoch) + 1u) & 3u;
        __syncthreads();
        const int j = bid - NSTR;
        float c[4][4];
#pragma unroll
        for (int mu = 0; mu < 4; mu++) c[mu][0] = c[mu][1] = c[mu][2] = c[mu][3] = 0.f;
        const uint32_t t0 = gtimer();
        const int zq = (warp * 32 + (t & 1) * 16 + (t >> 1) * 8 + g) * 4;
#pragma unroll 1
        for (int h = grp; h < NH; h += 2) {
            mbar_wait(smem_u32(&sm.full[h & 3]), (h >> 2) & 1);
            wo_job(c, h, j, warp, lane, tag, smem_u32(sm.ring) + (h & 3) * 32768, BAR_C + 2 * grp, grp ? sm.red : sm.ca,
                   grp ? sm.st : sm.ca + 512, t0, pace_ns16);
            if (lane == 0) mbar_arrive(smem_u32(&sm.empty[h & 3]));
            if (h >= NH - 6) {
                const float4 q4 = pick_quad(c, t);
                float4* hand = reinterpret_cast<float4*>(sm.wbuf) + warp * 32 + lane;
                if (grp == 0) {
                    *hand = q4;
                    if (h == NH - 2) bar_arrive<BAR_Q, 512>();
                } else {
                    if (h == NH - 1) bar_sync<BAR_Q, 512>();
                    const float4 ev = *hand;
                    const uint32_t tg = h == NH - 1 ? tag : tag ^ 3u;
                    const uint4 r = make_uint4(tagf(q4.x + ev.x, tg), tagf(q4.y + ev.y, tg), tagf(q4.z + ev.z, tg), tagf(q4.w + ev.w, tg));
                    st_pub16(g_run + j * 2 * DM + zq, r.x, r.y, r.z, r.w);
                }
            }
        }
        return;
    }

    if (wid < 8) {
        const int warp = wid & 3, g = lane >> 2, t = lane & 3;
        const int slot0 = cb * NH * UPB + tile;
        __syncthreads();
        if (wid >= 4) {
            const uint32_t koff = (warp * 16 + (lane & 15)) * 256;
            const uint32_t ksw = (lane * 2) & 7, kc0 = lane >> 4;
            uint32_t tag = 0;
#pragma unroll 1
            for (int h = 0; h < NH; h++) {
                if (h == 0) { bar_sync<BAR_Q, 320>(); tag = sm.tag; }
                if (h == 2) bar_sync<BAR_Q1, 320>();
                if (h == 8) bar_sync<BAR_Q2, 384>();
                uint4 qf[4];
#pragma unroll
                for (int i = 0; i < 4; i++) qf[i] = *reinterpret_cast<const uint4*>(sm.q + h * (DH / 2) + t * 16 + i * 4);
                const int st = (2 * h) % NSTAGE;
                mbar_wait(smem_u32(&sm.full[st]), (2 * h / NSTAGE) & 1);
                const uint32_t ka = smem_u32(sm.ring[st]) + koff;
                float c0[4] = {0.f, 0.f, 0.f, 0.f}, c1[4] = {0.f, 0.f, 0.f, 0.f};
#pragma unroll
                for (int i = 0; i < 4; i++) {
                    const int hf = i >> 1;
                    const uint4 a0 = ldsm(ka + hf * 128 + ((((i & 1) * 4 + kc0) ^ (ksw + hf)) << 4));
                    const uint4 a1 = ldsm(ka + hf * 128 + ((((i & 1) * 4 + 2 + kc0) ^ (ksw + hf)) << 4));
                    mma_bf16(c0, a0, qf[i].x, qf[i].y);
                    mma_bf16(c1, a1, qf[i].z, qf[i].w);
                }
                const uint32_t sr = cvt2(c0[0] + c1[0], c0[2] + c1[2]);
                const uint32_t s2 = cvt2(bf_lo(sr) * 0.08838834764831845f, bf_hi(sr) * 0.08838834764831845f);
                const float sa = bf_lo(s2), sb = bf_hi(s2);
                float m = fmaxf(sa, sb);
                m = fmaxf(m, __shfl_xor_sync(0xffffffffu, m, 4));
                if (lane == 0) mbar_arrive(smem_u32(&sm.empty[st]));
                m = fmaxf(m, __shfl_xor_sync(0xffffffffu, m, 8));
                m = fmaxf(m, __shfl_xor_sync(0xffffffffu, m, 16));
                float* cs = sm.cst + (h & 1) * 8;
                if (lane == 0) cs[warp] = m;
                bar_sync<BAR_C, 128>();
                const float4 ma = *reinterpret_cast<const float4*>(cs);
                m = fmaxf(fmaxf(ma.x, ma.y), fmaxf(ma.z, ma.w));
                const float pa = ex2((sa - m) * LOG2E), pb = ex2((sb - m) * LOG2E);
                float l = pa + pb;
                l += __shfl_xor_sync(0xffffffffu, l, 4);
                {
                    const float pv = (t & 2) ? pb : pa;
                    const uint32_t hi = cvt2(pv, 0.f);
                    const uint32_t w16 = (t & 1) ? cvt2(pv - bf_lo(hi), 0.f) : hi;
                    sm.ps[(h & 7) * 128 + (((t & 1) * 4 + (g >> 1)) * 8 + warp * 2 + (t >> 1)) * 2 + (g & 1)] = (unsigned short)w16;
                }
                l += __shfl_xor_sync(0xffffffffu, l, 8);
                l += __shfl_xor_sync(0xffffffffu, l, 16);
                __syncwarp();
                if (lane == 0) { cs[4 + warp] = l; mbar_arrive(smem_u32(&sm.pfull[h & 7])); }
                if (warp != 3) {
                    bar_arrive<BAR_L, 128>();
                    if (h + 2 < NH) {
                        if (warp == 0) st_pub4(g_pml + (slot0 + (h + 2) * UPB) * 32 + lane, ~tag);
                        if (warp == 1) st_pub16(g_po + (slot0 + (h + 2) * UPB) * DH + lane * 4, ~tag, ~tag, ~tag, ~tag);
                    }
                } else {
                    bar_sync<BAR_L, 128>();
                    const float4 la = *reinterpret_cast<const float4*>(cs + 4);
                    if (lane < 16) st_pub8(g_pml + (slot0 + h * UPB) * 32 + lane * 2, tagf(m, tag), tagf((la.x + la.y) + (la.z + la.w), tag));
                }
            }
        } else {
            const uint32_t voff = (lane & 15) * 256 + (warp >> 1) * 128 + ((((warp & 1) * 4 + (lane >> 4)) ^ ((lane * 2 + (warp >> 1)) & 7)) << 4);
            const bool h8 = lane & 8;
            bar_sync<BAR_Q, 320>();
            const uint32_t tag = sm.tag;
#pragma unroll 1
            for (int h = 0; h < NH; h++) {
                mbar_wait(smem_u32(&sm.pfull[h & 7]), (h >> 3) & 1);
                uint4 pa = make_uint4(0u, 0u, 0u, 0u), pb = pa;
                if (lane < 16) {
                    pa = *reinterpret_cast<const uint4*>(sm.ps + (h & 7) * 128 + (lane & 7) * 16);
                    pb = *reinterpret_cast<const uint4*>(sm.ps + (h & 7) * 128 + (lane & 7) * 16 + 8);
                }
                const int st = (2 * h + 1) % NSTAGE;
                mbar_wait(smem_u32(&sm.full[st]), ((2 * h + 1) / NSTAGE) & 1);
                const uint32_t va = smem_u32(sm.ring[st]) + voff;
                float c[8][4];
#pragma unroll
                for (int i = 0; i < 8; i++) c[i][0] = c[i][1] = c[i][2] = c[i][3] = 0.f;
#pragma unroll
                for (int s = 0; s < 4; s++) {
                    const uint4 v0 = ldsm_t(va + s * 4096), v1 = ldsm_t((va ^ 32) + s * 4096);
                    const uint4 a = s == 0 ? make_uint4(pa.x, 0u, pa.y, 0u) : s == 1 ? make_uint4(pa.z, 0u, pa.w, 0u)
                                  : s == 2 ? make_uint4(pb.x, 0u, pb.y, 0u) : make_uint4(pb.z, 0u, pb.w, 0u);
                    mma_bf16(c[(s & 1) * 4 + 0], a, v0.x, v0.y); mma_bf16(c[(s & 1) * 4 + 1], a, v0.z, v0.w);
                    mma_bf16(c[(s & 1) * 4 + 2], a, v1.x, v1.y); mma_bf16(c[(s & 1) * 4 + 3], a, v1.z, v1.w);
                }
                float o0 = h8 ? c[2][0] + c[6][0] : c[0][0] + c[4][0], o1 = h8 ? c[2][1] + c[6][1] : c[0][1] + c[4][1];
                float o2 = h8 ? c[3][0] + c[7][0] : c[1][0] + c[5][0], o3 = h8 ? c[3][1] + c[7][1] : c[1][1] + c[5][1];
                o0 += __shfl_down_sync(0xffffffffu, o0, 4); o1 += __shfl_down_sync(0xffffffffu, o1, 4);
                o2 += __shfl_down_sync(0xffffffffu, o2, 4); o3 += __shfl_down_sync(0xffffffffu, o3, 4);
                if ((lane & 20) == 0)
                    st_pub16(g_po + (slot0 + h * UPB) * DH + warp * 32 + (lane & 8) * 2 + (lane & 3) * 4,
                             tagf(o0, tag), tagf(o1, tag), tagf(o2, tag), tagf(o3, tag));
                if (lane == 0) {
                    mbar_arrive(smem_u32(&sm.empty[st]));
                    if (warp == 0) sm.done = h + 1;
                }
            }
        }
        return;
    }

    const int tid = threadIdx.x - 256, warp = wid - 8;
    const int g = lane >> 2, t = lane & 3;
    const int b = lane >> 4;
    const int k0 = warp * 64 + (lane & 12) * 4 + t * 2;
    const uint32_t xa = *reinterpret_cast<const uint32_t*>(x + b * DM + k0), xb = *reinterpret_cast<const uint32_t*>(x + b * DM + k0 + 8);
    const uint32_t epoch = ld_poll4(&g_epoch);
    {
        const int row = tid >> 2;
        const uint32_t dst = wb + row * 64 + (((tid & 3) ^ ((row >> 1) & 3)) << 4);
        const __nv_bfloat16* src = wq + (size_t)row * (NH * DH) + bid * 32 + (tid & 3) * 8;
#pragma unroll
        for (int i = 0; i < 8; i++) cp_async16(dst + i * 4096, src + (size_t)i * 64 * (NH * DH));
    }
    const uint32_t tag = (epoch + 1u) & 3u;
    const int lrow = (lane & 7) + (lane >> 4) * 8;
    const int zq = (warp * 32 + (t & 1) * 16 + (t >> 1) * 8 + g) * 4;

    {
        __syncthreads();
        uint32_t* qo = g_q + ((tid >> 5) & 1) * (NH * DH) + bid * 32 + (tid & 31);
        if (tid < 64) st_pub4(qo, ~tag);
        float v[4] = {bf_lo(xa), bf_hi(xa), bf_lo(xb), bf_hi(xb)};
        layernorm_2x512(v, sm.st, warp, lane);
        uint4 wqr[4][2];
        asm volatile("cp.async.wait_all;" ::: "memory");
        bar_sync<BAR_H, 256>();
#pragma unroll
        for (int mu = 0; mu < 2; mu++) {
            const uint32_t a = wb + (warp * 64 + lrow) * 64 + (((2 * mu + ((lane >> 3) & 1)) ^ ((lrow >> 1) & 3)) << 4);
#pragma unroll
            for (int s = 0; s < 4; s++) wqr[s][mu] = ldsm_t(a + s * 1024);
        }
        gemv32(wqr, cvt2(v[0], v[1]), cvt2(v[2], v[3]), sm.red, warp, lane);
        bar_sync<BAR_H, 256>();
        if (tid < 64) {
            float acc = 0.f;
#pragma unroll
            for (int wv = 0; wv < 8; wv++) acc += sm.red[wv * 144 + (tid >> 5) * 36 + (tid & 31)];
            st_pub4(qo, __float_as_uint(rbf(acc)) | tag);
        }
        const int qt = (tid + 64) & 255;
        const uint32_t* qp = g_q + cb * NH * DH + qt * 4;
        uint4 u0[1], u[3];
        poll_all(u0, qp, 0, tag);
        uint32_t* qs = sm.q + (qt >> 5) * 64 + (lane & 1) * 32 + (lane >> 1);
        qs[0] = __byte_perm(u0[0].x, u0[0].y, 0x7632); qs[16] = __byte_perm(u0[0].z, u0[0].w, 0x7632);
        if (tid == 255) sm.tag = tag;
        if (warp >= 6) bar_arrive<BAR_Q, 320>(); else bar_arrive<BAR_Q1, 320>();
        poll_all(u, qp + 1024, 1024, tag);
#pragma unroll
        for (int i = 0; i < 3; i++) {
            qs[(i + 1) * 512] = __byte_perm(u[i].x, u[i].y, 0x7632);
            qs[(i + 1) * 512 + 16] = __byte_perm(u[i].z, u[i].w, 0x7632);
        }
        bar_arrive<BAR_Q2, 384>();
    }
    if (bid >= NFFN + NRED) return;
    const int kq = warp * 64 + (lane & 8) * 4 + (lane & 7);
    const uint32_t* hp = g_run + tid * 4;
    float xv[4];
#pragma unroll
    for (int r = 0; r < 4; r++) xv[r] = __bfloat162float(x[b * DM + kq + 8 * r]);
    if (bid < NFFN) {
        uint32_t* yo = g_yp + ((zq >> 5) * NFFN + bid) * 32 + (zq & 31);
        const int k = tid >> 1, ii = ((k >> 5) & 1) * 8 + (k & 7), rr = (k >> 3) & 3;
        const int sl = (k & 64) + (ii >> 2) * 16 + (ii & 3) * 2 + (rr & 1) + (rr >> 1) * 8;
        const uint32_t gdst = wb + sl * 32 + (((tid & 1) ^ ((sl >> 2) & 1)) << 4);
        const int gsrc = k * FF + bid * 16 + (tid & 1) * 8;
        wait_ge(&sm.done, NH - 4, 1000);
        st_pub16(yo, ~tag, ~tag, ~tag, ~tag);
        wait_ge(&sm.go, 1);
#pragma unroll
        for (int i = 0; i < 4; i++) cp_async16(gdst + i * 4096, wg + gsrc + i * 128 * FF);
        wait_ge(&sm.go, 2);
#pragma unroll
        for (int i = 0; i < 4; i++) cp_async16(gdst + 16384 + i * 4096, wu + gsrc + i * 128 * FF);
        asm volatile("cp.async.wait_all;" ::: "memory");
        bar_sync<BAR_H, 256>();
        uint4 wf[4][2], d[4];
#pragma unroll
        for (int mu = 0; mu < 2; mu++) {
            const uint32_t a = wb + mu * 16384 + (warp * 64 + lrow) * 32 + ((((lane >> 3) & 1) ^ ((lrow >> 2) & 1)) << 4);
#pragma unroll
            for (int s = 0; s < 4; s++) wf[s][mu] = ldsm_t(a + s * 512);
        }
        uint4 u[4];
        poll_all(u, hp, 2 * DM, tag);
        uint32_t p0 = cvt2(sum4(u, 0), sum4(u, 1)), p1 = cvt2(sum4(u, 2), sum4(u, 3));
        p0 = cvt2(xv[0] + bf_lo(p0), xv[1] + bf_hi(p0)); p1 = cvt2(xv[2] + bf_lo(p1), xv[3] + bf_hi(p1));
        gemv32(wf, p0, p1, sm.red, warp, lane);
        const float v[4] = {bf_lo(p0), bf_hi(p0), bf_lo(p1), bf_hi(p1)};
        ln_part1(v, sm.st, warp, lane);
        bar_sync<BAR_H, 256>();
        mbar_wait(smem_u32(&sm.dfull), 0);
#pragma unroll
        for (int mu = 0; mu < 4; mu++)
            d[mu] = ldsm_t(smem_u32(sm.ring[(2 * NH) % NSTAGE]) + warp * 2048 + lrow * 128 + (((2 * mu + ((lane >> 3) & 1)) ^ (lane & 7)) << 4));
        const float* rp = sm.red + b * 52 + (lane & 15);
        const float* rq = sm.red + b * 20 + 16 + (lane & 15);
        const float* rs = sm.red + 72 + lane;
        float gs = rp[0], us = rq[0], gt = rp[144], ut = rq[144], s0 = rs[0], s1 = rs[144];
#pragma unroll
        for (int wv = 2; wv < 8; wv += 2) {
            gs += rp[wv * 144]; us += rq[wv * 144]; s0 += rs[wv * 144];
            gt += rp[wv * 144 + 144]; ut += rq[wv * 144 + 144]; s1 += rs[wv * 144 + 144];
        }
        gt += gs; ut += us; s0 += s1;
        s1 = __shfl_xor_sync(0xffffffffu, s0, 16);
        gs = b ? ut : gt; us = b ? gt : ut;
        const float sg = b ? s1 : s0, su = b ? s0 : s1;
        float mr, inv;
        ln_part2(sm.st, b, mr, inv);
        const float gv = rbf(fmaf(-mr, sg, gs) * inv), uv = rbf(fmaf(-mr, su, us) * inv);
        const float act = rbf(gv * rcp(1.0f + ex2(-LOG2E * gv))) * uv;
        const uint32_t pr = cvt2(act, __shfl_down_sync(0xffffffffu, act, 1));
        const int src = ((g & 1) << 4) + 2 * t;
        const uint32_t b0 = __shfl_sync(0xffffffffu, pr, src), b1 = __shfl_sync(0xffffffffu, pr, src + 8);
        float c[4][4];
#pragma unroll
        for (int mu = 0; mu < 4; mu++) { c[mu][0] = c[mu][1] = c[mu][2] = c[mu][3] = 0.f; mma_bf16(c[mu], d[mu], b0, b1); }
        const float4 r = pick_quad(c, t);
        st_pub16(yo, tagf(r.x, tag), tagf(r.y, tag), tagf(r.z, tag), tagf(r.w, tag));
    } else {
        const int fr = bid - NFFN;
        float* ha = reinterpret_cast<float*>(sm.wbuf);
        float wv4[4];
#pragma unroll
        for (int r = 0; r < 4; r++) wv4[r] = __bfloat162float(wr[kq + 8 * r]);
        const int ob = (fr >> 1) & 1, oc = (fr >> 2) * 64 + (fr & 1) * 32 + g + 8 * t;
        const int vi = warp * 4 + (lane >> 3);
        const uint32_t* yp = g_yp + (fr * NFFN + vi) * 32 + (lane & 7) * 4;
        wait_ge(&sm.done, NH - 3, 1000);
        wait_ge(&sm.done, NH);
        uint4 y[3], u[4];
        poll_all(u, hp, 2 * DM, tag);
        float v[4];
#pragma unroll
        for (int r = 0; r < 4; r++) v[r] = rbf(xv[r] + rbf(sum4(u, r)));
        *reinterpret_cast<float4*>(ha + tid * 4) = make_float4(v[0], v[1], v[2], v[3]);
        ln_part1(v, sm.st, warp, lane);
        bar_sync<BAR_H, 256>();
        float mr, inv;
        ln_part2(sm.st, b, mr, inv);
#pragma unroll
        for (int i = 0; i < 4; i++) v[i] = rbf(rbf(v[i] - mr) * inv);
        float rp = (v[0] * wv4[0] + v[1] * wv4[1]) + (v[2] * wv4[2] + v[3] * wv4[3]);
#pragma unroll
        for (int o = 1; o < 16; o <<= 1) rp += __shfl_xor_sync(0xffffffffu, rp, o);
        if ((lane & 15) == 0) sm.st[32 + b * 8 + warp] = rp;
        mr = __shfl_sync(0xffffffffu, mr, ob << 4); inv = __shfl_sync(0xffffffffu, inv, ob << 4);
        const float hv2 = ha[fr * 32 + lane];
        const float hn = rbf(rbf(hv2 - mr) * inv);
        bar_sync<BAR_H, 256>();
        const float4 ra = *reinterpret_cast<const float4*>(sm.st + 32 + ob * 8);
        const float4 rb = *reinterpret_cast<const float4*>(sm.st + 36 + ob * 8);
        const float rr = rbf(((ra.x + ra.y) + (ra.z + ra.w)) + ((rb.x + rb.y) + (rb.z + rb.w)));
        const float sig = rbf(rcp(1.0f + ex2(-LOG2E * rr)));
        poll_all(y, yp, 27 * 32, tag);
        float a[4] = {untag(y[2].x), untag(y[2].y), untag(y[2].z), untag(y[2].w)};
        if (vi < 27) { acc4(a, y[0]); acc4(a, y[1]); }
        sm.red[warp * 32 + (lane & 7) * 4 + (lane >> 3)] = fold_t(a, lane);
        if (warp != 0) {
            bar_arrive<BAR_H, 256>();
        } else {
            bar_sync<BAR_H, 256>();
            float s0 = sm.red[lane], s1 = sm.red[32 + lane];
#pragma unroll
            for (int wv = 2; wv < 8; wv += 2) { s0 += sm.red[wv * 32 + lane]; s1 += sm.red[wv * 32 + 32 + lane]; }
            const float upd = rbf(hn * 0.0f + rbf(rbf(s0 + s1) * sig));
            reinterpret_cast<unsigned short*>(out)[ob * DM + oc] = (unsigned short)cvt2(hv2 + rbf(hn + upd), 0.f);
            if (fr == 0 && lane == 0) st_pub4(&g_epoch, epoch + 1u);
        }
    }
}

typedef CUresult (*EncodeFn)(CUtensorMap*, CUtensorMapDataType, cuuint32_t, void*, const cuuint64_t*, const cuuint64_t*,
                             const cuuint32_t*, const cuuint32_t*, CUtensorMapInterleave, CUtensorMapSwizzle,
                             CUtensorMapL2promotion, CUtensorMapFloatOOBfill);

int make_map_rows(EncodeFn fn, CUtensorMap* tm, const void* base, int rows, int box_rows, int nb) {
    const cuuint64_t dims[3] = {64u, (cuuint64_t)rows, (cuuint64_t)nb};
    const cuuint64_t strides[2] = {(cuuint64_t)(nb * 128), 128u};
    const cuuint32_t box[3] = {64u, (cuuint32_t)box_rows, (cuuint32_t)nb};
    const cuuint32_t es[3] = {1u, 1u, 1u};
    return (int)fn(tm, CU_TENSOR_MAP_DATA_TYPE_BFLOAT16, 3, const_cast<void*>(base), dims, strides, box, es,
       CU_TENSOR_MAP_INTERLEAVE_NONE, CU_TENSOR_MAP_SWIZZLE_128B, CU_TENSOR_MAP_L2_PROMOTION_L2_128B, CU_TENSOR_MAP_FLOAT_OOB_FILL_NONE);
}

}

extern "C" void kernel_launch(void* const* d_in, const int* in_sizes, int n_in, void* d_out, int out_size) {
    (void)in_sizes; (void)n_in; (void)out_size;
    static int pace_ns16 = 0;
    static EncodeFn encode = nullptr;
    if (pace_ns16 == 0) {
        int dev = 0, khz = 0, bits = 0;
        cudaGetDevice(&dev);
        cudaDeviceGetAttribute(&khz, cudaDevAttrMemoryClockRate, dev);
        cudaDeviceGetAttribute(&bits, cudaDevAttrGlobalMemoryBusWidth, dev);
        double bw = 2.0 * khz * 1e3 * (bits / 8) * 1e-9 * PACE_EFF;
        if (!(bw > 100.0)) bw = 3300.0;
        pace_ns16 = (int)(16.0 * NCTA * TILE_BYTES / bw);
        cudaFuncSetAttribute(fused_decode_kernel, cudaFuncAttributeMaxDynamicSharedMemorySize, (int)sizeof(Smem));
        cudaDriverEntryPointQueryResult qr;
        cudaGetDriverEntryPoint("cuTensorMapEncodeTiled", (void**)&encode, cudaEnableDefault, &qr);
    }
    CUtensorMap to, td, tk, tv;
    if (!encode || make_map_rows(encode, &to, d_in[4], NH * DH, 32, 8) || make_map_rows(encode, &td, d_in[9], FF, 16, 8) ||
        make_map_rows(encode, &tk, d_in[1], 4 * NH * SK, 2 * UKEYS, 1) || make_map_rows(encode, &tv, d_in[2], 4 * NH * SK, 2 * UKEYS, 1))
        return;
    fused_decode_kernel<<<NCTA, NTHREADS, sizeof(Smem)>>>(
        to, td, tk, tv, (const __nv_bfloat16*)d_in[3], (const __nv_bfloat16*)d_in[0],
        (const __nv_bfloat16*)d_in[6], (const __nv_bfloat16*)d_in[7], (const __nv_bfloat16*)d_in[8],
        (__nv_bfloat16*)d_out, pace_ns16);
}
```
